```python
import torch

def _softmax(x, axis=-1):
    return torch.softmax(x, dim=axis)
def _gelu(x):
    return torch.nn.functional.gelu(x, approximate="tanh")
def _silu(x):
    return torch.nn.functional.silu(x)
def _sigmoid(x):
    return torch.sigmoid(x)
def _layernorm(x, axis=-1, eps=1e-5):
    m = x.mean(dim=axis, keepdim=True)
    v = x.var(dim=axis, keepdim=True, unbiased=False)
    return (x - m) / torch.sqrt(v + eps)
def _scatter_add(tgt, idx, src, axis=0):
    return tgt.clone().index_add_(axis, idx, src)
def _segment_sum(src, seg, n):
    out = torch.zeros((n,) + src.shape[1:], dtype=src.dtype)
    return out.index_add_(0, seg, src)
def _pad(x, pw):
    flat = tuple(v for pair in reversed(pw) for v in pair)
    return torch.nn.functional.pad(x, flat)

kernel_name = 'sequential_preLN__linear_attn_block__dense_activation_gelu__prompt'

def setup_inputs():

    _w = (lambda a: (lambda t: t.to(torch.bfloat16) if t.is_floating_point() else t)(torch.as_tensor(a)))
    def _A_setup():
        B, S, D = 1, 2048, 640
        return {
            "x": _w((lambda *s: torch.randn(*s, dtype=torch.bfloat16) * 0.05)(B, S, D)),
            "wqkv": _w((lambda *s: torch.randn(*s, dtype=torch.bfloat16) * 0.05)(D, 3 * D)),
            "wo": _w((lambda *s: torch.randn(*s, dtype=torch.bfloat16) * 0.05)(D, D)),
        }
    _A_in = _A_setup()

    def _B_setup():
        B, S, D, F = 1, 2048, 640, 1536
        return {
            "x": _w((lambda *s: torch.randn(*s, dtype=torch.bfloat16) * 0.05)(B, S, D)),
            "w1": _w((lambda *s: torch.randn(*s, dtype=torch.bfloat16) * 0.8)(D, F) * (D ** -0.5)),
            "b1": _w((lambda *s: torch.randn(*s, dtype=torch.bfloat16) * 12.8)(F) * 0.01),
            "w2": _w((lambda *s: torch.randn(*s, dtype=torch.bfloat16) * 0.2)(F, D) * (F ** -0.5)),
            "b2": _w((lambda *s: torch.randn(*s, dtype=torch.bfloat16) * 3.2)(D) * 0.01),
        }
    _B_in = _B_setup()

    return {
        "A_x": _A_in["x"],
        "A_wqkv": _A_in["wqkv"],
        "A_wo": _A_in["wo"],
        "B_x": _B_in["x"],
        "B_w1": _B_in["w1"],
        "B_b1": _B_in["b1"],
        "B_w2": _B_in["w2"],
        "B_b2": _B_in["b2"],
    }

def reference(A_x, A_wqkv, A_wo, B_x, B_w1, B_b1, B_w2, B_b2):
    def _A_ref(x, wqkv, wo):
        B, S, D = x.shape
        H = 32; Dh = D // H
        qkv = (lambda x, *d: x.permute(*d))((x @ wqkv).reshape(B, S, 3, H, Dh), 2, 0, 3, 1, 4)
        q, k, v = qkv[0], qkv[1], qkv[2]
        phi = lambda t: torch.where(t > 0, t + 1, torch.exp(t)) + 1e-6
        pq, pk = phi(q), phi(k)
        kv = torch.einsum("bhsd,bhse->bhde", pk, v)
        z = torch.einsum("bhsd->bhd", pk)
        num = torch.einsum("bhqd,bhde->bhqe", pq, kv)
        den = torch.einsum("bhqd,bhd->bhq", pq, z)[..., None] + 1e-6
        o = num / den
        return (lambda x, *d: x.permute(*d))(o, 0, 2, 1, 3).reshape(B, S, D) @ wo

    def _B_ref(x, w1, b1, w2, b2):
        h = torch.einsum("bsd,df->bsf", x, w1) + b1
        h = _gelu(h)
        return torch.einsum("bsf,fd->bsd", h, w2) + b2

    x = A_x
    h = x + _A_ref(_layernorm(x, axis=-1), A_wqkv, A_wo)
    h2 = h + _B_ref(_layernorm(h, axis=-1), B_w1, B_b1, B_w2, B_b2)
    return h2
```

```cpp
#include <cuda_runtime.h>
#include <cuda_bf16.h>
#include <cuda.h>
#include <stdint.h>
#include <type_traits>

namespace {

template <int TA, int TB>
__device__ __forceinline__ void wgmma_ss_n8(float (&d)[4], uint64_t da, uint64_t oa, uint64_t db, uint64_t ob, int sc) {
  asm volatile("{.reg .pred p; .reg .b64 da, db; setp.ne.b32 p, %8, 0; add.u64 da, %4, %5; add.u64 db, %6, %7;\n"
    "wgmma.mma_async.sync.aligned.m64n8k16.f32.bf16.bf16 {%0,%1,%2,%3}, da, db, p, 1, 1, %9, %10;}\n"
    : "+f"(d[0]),"+f"(d[1]),"+f"(d[2]),"+f"(d[3])
    : "l"(da), "l"(oa), "l"(db), "l"(ob), "r"(sc), "n"(TA), "n"(TB));
}
template <int TA, int TB>
__device__ __forceinline__ void wgmma_ss_n40(float (&d)[20], uint64_t da, uint64_t oa, uint64_t db, uint64_t ob, int sc) {
  asm volatile("{.reg .pred p; .reg .b64 da, db; setp.ne.b32 p, %24, 0; add.u64 da, %20, %21; add.u64 db, %22, %23;\n"
    "wgmma.mma_async.sync.aligned.m64n40k16.f32.bf16.bf16 {%0,%1,%2,%3,%4,%5,%6,%7,%8,%9,%10,%11,%12,%13,%14,%15,%16,%17,%18,%19}, da, db, p, 1, 1, %25, %26;}\n"
    : "+f"(d[0]),"+f"(d[1]),"+f"(d[2]),"+f"(d[3]),"+f"(d[4]),"+f"(d[5]),"+f"(d[6]),"+f"(d[7]),"+f"(d[8]),"+f"(d[9]),"+f"(d[10]),"+f"(d[11]),"+f"(d[12]),"+f"(d[13]),"+f"(d[14]),"+f"(d[15]),"+f"(d[16]),"+f"(d[17]),"+f"(d[18]),"+f"(d[19])
    : "l"(da), "l"(oa), "l"(db), "l"(ob), "r"(sc), "n"(TA), "n"(TB));
}
template <int TB>
__device__ __forceinline__ void wgmma_rs_n48(float (&d)[24], uint32_t a0, uint32_t a1, uint32_t a2, uint32_t a3, uint64_t db, uint64_t ob, int sc) {
  asm volatile("{.reg .pred p; .reg .b64 db; setp.ne.b32 p, %30, 0; add.u64 db, %28, %29;\n"
    "wgmma.mma_async.sync.aligned.m64n48k16.f32.bf16.bf16 {%0,%1,%2,%3,%4,%5,%6,%7,%8,%9,%10,%11,%12,%13,%14,%15,%16,%17,%18,%19,%20,%21,%22,%23}, {%24,%25,%26,%27}, db, p, 1, 1, %31;}\n"
    : "+f"(d[0]),"+f"(d[1]),"+f"(d[2]),"+f"(d[3]),"+f"(d[4]),"+f"(d[5]),"+f"(d[6]),"+f"(d[7]),"+f"(d[8]),"+f"(d[9]),"+f"(d[10]),"+f"(d[11]),"+f"(d[12]),"+f"(d[13]),"+f"(d[14]),"+f"(d[15]),"+f"(d[16]),"+f"(d[17]),"+f"(d[18]),"+f"(d[19]),"+f"(d[20]),"+f"(d[21]),"+f"(d[22]),"+f"(d[23])
    : "r"(a0), "r"(a1), "r"(a2), "r"(a3), "l"(db), "l"(ob), "r"(sc), "n"(TB));
}
template <int TB>
__device__ __forceinline__ void wgmma_rs_n80(float (&d)[40], uint32_t a0, uint32_t a1, uint32_t a2, uint32_t a3, uint64_t db, uint64_t ob, int sc) {
  asm volatile("{.reg .pred p; .reg .b64 db; setp.ne.b32 p, %46, 0; add.u64 db, %44, %45;\n"
    "wgmma.mma_async.sync.aligned.m64n80k16.f32.bf16.bf16 {%0,%1,%2,%3,%4,%5,%6,%7,%8,%9,%10,%11,%12,%13,%14,%15,%16,%17,%18,%19,%20,%21,%22,%23,%24,%25,%26,%27,%28,%29,%30,%31,%32,%33,%34,%35,%36,%37,%38,%39}, {%40,%41,%42,%43}, db, p, 1, 1, %47;}\n"
    : "+f"(d[0]),"+f"(d[1]),"+f"(d[2]),"+f"(d[3]),"+f"(d[4]),"+f"(d[5]),"+f"(d[6]),"+f"(d[7]),"+f"(d[8]),"+f"(d[9]),"+f"(d[10]),"+f"(d[11]),"+f"(d[12]),"+f"(d[13]),"+f"(d[14]),"+f"(d[15]),"+f"(d[16]),"+f"(d[17]),"+f"(d[18]),"+f"(d[19]),"+f"(d[20]),"+f"(d[21]),"+f"(d[22]),"+f"(d[23]),"+f"(d[24]),"+f"(d[25]),"+f"(d[26]),"+f"(d[27]),"+f"(d[28]),"+f"(d[29]),"+f"(d[30]),"+f"(d[31]),"+f"(d[32]),"+f"(d[33]),"+f"(d[34]),"+f"(d[35]),"+f"(d[36]),"+f"(d[37]),"+f"(d[38]),"+f"(d[39])
    : "r"(a0), "r"(a1), "r"(a2), "r"(a3), "l"(db), "l"(ob), "r"(sc), "n"(TB));
}
template <int TA, int TB>
__device__ __forceinline__ void wgmma_ss_n80(float (&d)[40], uint64_t da, uint64_t oa, uint64_t db, uint64_t ob, int sc) {
  asm volatile("{.reg .pred p; .reg .b64 da, db; setp.ne.b32 p, %44, 0; add.u64 da, %40, %41; add.u64 db, %42, %43;\n"
    "wgmma.mma_async.sync.aligned.m64n80k16.f32.bf16.bf16 {%0,%1,%2,%3,%4,%5,%6,%7,%8,%9,%10,%11,%12,%13,%14,%15,%16,%17,%18,%19,%20,%21,%22,%23,%24,%25,%26,%27,%28,%29,%30,%31,%32,%33,%34,%35,%36,%37,%38,%39}, da, db, p, 1, 1, %45, %46;}\n"
    : "+f"(d[0]),"+f"(d[1]),"+f"(d[2]),"+f"(d[3]),"+f"(d[4]),"+f"(d[5]),"+f"(d[6]),"+f"(d[7]),"+f"(d[8]),"+f"(d[9]),"+f"(d[10]),"+f"(d[11]),"+f"(d[12]),"+f"(d[13]),"+f"(d[14]),"+f"(d[15]),"+f"(d[16]),"+f"(d[17]),"+f"(d[18]),"+f"(d[19]),"+f"(d[20]),"+f"(d[21]),"+f"(d[22]),"+f"(d[23]),"+f"(d[24]),"+f"(d[25]),"+f"(d[26]),"+f"(d[27]),"+f"(d[28]),"+f"(d[29]),"+f"(d[30]),"+f"(d[31]),"+f"(d[32]),"+f"(d[33]),"+f"(d[34]),"+f"(d[35]),"+f"(d[36]),"+f"(d[37]),"+f"(d[38]),"+f"(d[39])
    : "l"(da), "l"(oa), "l"(db), "l"(ob), "r"(sc), "n"(TA), "n"(TB));
}
template <int TA, int TB>
__device__ __forceinline__ void wgmma_ss_n96(float (&d)[48], uint64_t da, uint64_t oa, uint64_t db, uint64_t ob, int sc) {
  asm volatile("{.reg .pred p; .reg .b64 da, db; setp.ne.b32 p, %52, 0; add.u64 da, %48, %49; add.u64 db, %50, %51;\n"
    "wgmma.mma_async.sync.aligned.m64n96k16.f32.bf16.bf16 {%0,%1,%2,%3,%4,%5,%6,%7,%8,%9,%10,%11,%12,%13,%14,%15,%16,%17,%18,%19,%20,%21,%22,%23,%24,%25,%26,%27,%28,%29,%30,%31,%32,%33,%34,%35,%36,%37,%38,%39,%40,%41,%42,%43,%44,%45,%46,%47}, da, db, p, 1, 1, %53, %54;}\n"
    : "+f"(d[0]),"+f"(d[1]),"+f"(d[2]),"+f"(d[3]),"+f"(d[4]),"+f"(d[5]),"+f"(d[6]),"+f"(d[7]),"+f"(d[8]),"+f"(d[9]),"+f"(d[10]),"+f"(d[11]),"+f"(d[12]),"+f"(d[13]),"+f"(d[14]),"+f"(d[15]),"+f"(d[16]),"+f"(d[17]),"+f"(d[18]),"+f"(d[19]),"+f"(d[20]),"+f"(d[21]),"+f"(d[22]),"+f"(d[23]),"+f"(d[24]),"+f"(d[25]),"+f"(d[26]),"+f"(d[27]),"+f"(d[28]),"+f"(d[29]),"+f"(d[30]),"+f"(d[31]),"+f"(d[32]),"+f"(d[33]),"+f"(d[34]),"+f"(d[35]),"+f"(d[36]),"+f"(d[37]),"+f"(d[38]),"+f"(d[39]),"+f"(d[40]),"+f"(d[41]),"+f"(d[42]),"+f"(d[43]),"+f"(d[44]),"+f"(d[45]),"+f"(d[46]),"+f"(d[47])
    : "l"(da), "l"(oa), "l"(db), "l"(ob), "r"(sc), "n"(TA), "n"(TB));
}

__device__ __align__(1024) unsigned char g_o[16 * 2 * 40 * 2048];
__device__ __align__(1024) unsigned char g_h[16 * 2 * 40 * 2048];
__device__ __align__(1024) unsigned char g_g[16 * 2 * 96 * 2048];
struct Small {
  uint32_t epoch[32];
  uint32_t flag[16 * 16 * 8];
  uint32_t zflag[8 * 8];
  uint4 rs[16 * 128];
  uint2 cp[8 * 8 * 160];
  uint2 cs[640 + 1536 + 1280];
  float kv[8 * 2240];
  uint4 hstat[16 * 8 * 128];
};
__device__ __align__(1024) Small g_s;
#define g_flag g_s.flag
#define g_rs g_s.rs
#define g_cp g_s.cp
#define g_cs g_s.cs
#define g_kv g_s.kv
#define g_hstat g_s.hstat
#define REPAIR_CNT
#define TSB(idx)
#define TSG(idx)
#define TS(idx)
#define TSW(idx)

#define SLAB_AT 2
#define LATE_AT 8
#define ABL 0
#define GB2 2
#define ALT_END 0
#define GA2 4
__host__ __device__ constexpr int GA(int t) { return t <= GA2 ? 2 * t : (GA2 + t < 12 ? GA2 + t : 12); }
__host__ __device__ constexpr int GB(int t) { return t <= GB2 ? 2 * t : (GB2 + t < 12 ? GB2 + t : 12); }
constexpr int GBN = 12 - GB2;
constexpr int NS = 6, NS2 = 7;
constexpr uint32_t SM_B = 0, SM_A = 16384;
constexpr uint32_t SM_ST = 6 * 32768;
constexpr uint32_t SM_ROW = 229376;
constexpr uint32_t SM_COL = SM_ROW + 1024;
constexpr uint32_t SM_BAR = SM_COL + 1536;
constexpr uint32_t SMEM_BYTES = 232448;
constexpr uint32_t SM_V = SM_ST - 16384;
constexpr uint32_t SM_PK = SM_ST + 6144;
constexpr uint32_t SM_KVB = SM_ST + 20992;

enum : uint32_t {
  B_F = 0, B_E = 14, B_EA = 21, B_STAT1 = 28, B_STATQ, B_STAT2, B_KVP, B_KVB, B_KVEND, B_SLAB, B_LATE, B_HSEEN,
  B_GST  , B_GRDY = B_GST + 6  , B_COUNT = B_GRDY + 6
};

struct Params {
  CUtensorMap x, qkvM, qkvR, woM, woR, w1M, w1R, w2M, w2R, outM, outR, qkvS, w1S;
  const __nv_bfloat16 *px, *pwqkv, *pwo, *pw1, *pb1, *pw2, *pb2;
};

__device__ __forceinline__ void mbar_init(uint32_t a, uint32_t c) { asm volatile("mbarrier.init.shared::cta.b64 [%0], %1;" ::"r"(a), "r"(c) : "memory"); }
__device__ __forceinline__ void mbar_expect(uint32_t a, uint32_t b) { asm volatile("mbarrier.arrive.expect_tx.shared::cta.b64 _, [%0], %1;" ::"r"(a), "r"(b) : "memory"); }
__device__ __forceinline__ void mbar_arrive(uint32_t a) { asm volatile("mbarrier.arrive.shared::cta.b64 _, [%0];" ::"r"(a) : "memory"); }
__device__ __forceinline__ void mbar_arrive_if(uint32_t a, bool on) { asm volatile("{.reg .pred p; setp.ne.u32 p, %1, 0; @p mbarrier.arrive.shared::cta.b64 _, [%0];}" ::"r"(a), "r"((uint32_t)on) : "memory"); }
__device__ __forceinline__ void mbar_arrive2_if(uint32_t a, bool on) { asm volatile("{.reg .pred p; setp.ne.u32 p, %1, 0; @p mbarrier.arrive.shared::cta.b64 _, [%0], 2;}" ::"r"(a), "r"((uint32_t)on) : "memory"); }
__device__ __forceinline__ void mbar_wait(uint32_t a, uint32_t parity) {
  asm volatile(
      "{.reg .pred P, Q; .reg .u32 n;\n"
      "mov.u32 n, 0;\n"
      "LW:\n"
      "mbarrier.try_wait.parity.shared::cta.b64 P, [%0], %1;\n"
      "@P bra LD;\n"
      "add.u32 n, n, 1;\n"
      "setp.lt.u32 Q, n, 0x100000;\n"
      "@Q bra LW;\n"
      "trap;\n"
      "LD:\n}"
      ::"r"(a), "r"(parity) : "memory");
}
__device__ __forceinline__ uint32_t mbar_test(uint32_t a, uint32_t parity) {
  uint32_t ok;
  asm volatile("{.reg .pred P; mbarrier.test_wait.parity.shared::cta.b64 P, [%1], %2; selp.u32 %0, 1, 0, P;}" : "=r"(ok) : "r"(a), "r"(parity) : "memory");
  return ok;
}
__device__ __forceinline__ bool elect_one() {
  uint32_t p;
  asm volatile("{.reg .pred P; elect.sync _|P, 0xffffffff; selp.u32 %0, 1, 0, P;}" : "=r"(p));
  return p;
}
__device__ __forceinline__ void tma_ld(uint32_t dst, const CUtensorMap* m, int c0, int c1, uint32_t bar) {
  asm volatile("cp.async.bulk.tensor.2d.shared::cluster.global.mbarrier::complete_tx::bytes [%0], [%1, {%3, %4}], [%2];"
               ::"r"(dst), "l"(m), "r"(bar), "r"(c0), "r"(c1) : "memory");
}
__device__ __forceinline__ void tma_ld_mc(uint32_t dst, const CUtensorMap* m, int c0, int c1, uint32_t bar) {
  asm volatile("cp.async.bulk.tensor.2d.shared::cluster.global.mbarrier::complete_tx::bytes.multicast::cluster [%0], [%1, {%3, %4}], [%2], %5;"
               ::"r"(dst), "l"(m), "r"(bar), "r"(c0), "r"(c1), "h"((uint16_t)3) : "memory");
}
__device__ __forceinline__ void mbar_arrive_cl_if(uint32_t a, uint32_t c, bool on) { asm volatile("{.reg .pred p; setp.ne.u32 p, %2, 0; @p mbarrier.arrive.shared::cluster.b64 _, [%0], %1;}" ::"r"(a), "r"(c), "r"((uint32_t)on) : "memory"); }
__device__ __forceinline__ void mbar_arrive_cl1_if(uint32_t a, uint32_t on) { asm volatile("{.reg .pred p; setp.ne.u32 p, %1, 0; @p mbarrier.arrive.shared::cluster.b64 _, [%0];}" ::"r"(a), "r"(on) : "memory"); }
__device__ __forceinline__ void mbar_arrive_n_if(uint32_t a, uint32_t c, bool on) { asm volatile("{.reg .pred p; setp.ne.u32 p, %2, 0; @p mbarrier.arrive.shared::cta.b64 _, [%0], %1;}" ::"r"(a), "r"(c), "r"((uint32_t)on) : "memory"); }
__device__ __forceinline__ void st_rlx4_if(void* p, uint32_t x, uint32_t y, uint32_t z, uint32_t w, bool on) { asm volatile("{.reg .pred p; setp.ne.u32 p, %5, 0; @p st.relaxed.gpu.global.v4.u32 [%0], {%1,%2,%3,%4};}" ::"l"(p), "r"(x), "r"(y), "r"(z), "r"(w), "r"((uint32_t)on) : "memory"); }
struct Ring {
  uint32_t s = 0, ph = 0;
  template <int N> __device__ __forceinline__ void next() { if (++s == N) { s = 0; ph ^= 1; } }
  template <int N> __device__ __forceinline__ void skip(int n) { s += n; ph ^= (s / N) & 1; s %= N; }
  template <int N> __device__ __forceinline__ uint32_t prev() const { return s == 0 ? N - 1 : s - 1; }
};
__device__ __forceinline__ void tma_st(const CUtensorMap* m, uint32_t src, int c0, int c1) {
  asm volatile("cp.async.bulk.tensor.2d.global.shared::cta.bulk_group [%0, {%2, %3}], [%1];" ::"l"(m), "r"(src), "r"(c0), "r"(c1) : "memory");
}
__device__ __forceinline__ void bulk_ld(uint32_t dst, const void* src, uint32_t bytes, uint32_t bar) {
  asm volatile("cp.async.bulk.shared::cluster.global.mbarrier::complete_tx::bytes [%0], [%1], %2, [%3];" ::"r"(dst), "l"(src), "r"(bytes), "r"(bar) : "memory");
}
__device__ __forceinline__ void bulk_st(void* dst, uint32_t src, uint32_t bytes) {
  asm volatile("cp.async.bulk.global.shared::cta.bulk_group [%0], [%1], %2;" ::"l"(dst), "r"(src), "r"(bytes) : "memory");
}
__device__ __forceinline__ void bulk_red_f32(void* dst, uint32_t src, uint32_t bytes) {
  asm volatile("cp.reduce.async.bulk.global.shared::cta.bulk_group.add.f32 [%0], [%1], %2;" ::"l"(dst), "r"(src), "r"(bytes) : "memory");
}
__device__ __forceinline__ void bulk_commit() { asm volatile("cp.async.bulk.commit_group;" ::: "memory"); }
__device__ __forceinline__ void bulk_wait() { asm volatile("cp.async.bulk.wait_group 0;" ::: "memory"); }
__device__ __forceinline__ void bulk_wait_read() { asm volatile("cp.async.bulk.wait_group.read 0;" ::: "memory"); }
__device__ __forceinline__ void l2_prefetch(const void* p, uint32_t bytes) { asm volatile("cp.async.bulk.prefetch.L2.global [%0], %1;" ::"l"(p), "r"(bytes) : "memory"); }
__device__ __forceinline__ void fence_async_smem() { asm volatile("fence.proxy.async.shared::cta;" ::: "memory"); }
__device__ __forceinline__ void fence_async_gmem() { asm volatile("fence.proxy.async.global;" ::: "memory"); }
__device__ __forceinline__ void bar_sync(int id, int n) { asm volatile("bar.sync %0, %1;" ::"r"(id), "r"(n) : "memory"); }
__device__ __forceinline__ void bar_arrive(int id, int n) { asm volatile("bar.arrive %0, %1;" ::"r"(id), "r"(n) : "memory"); }
__device__ __forceinline__ void st_flag(uint32_t* p, uint32_t v) { asm volatile("st.relaxed.gpu.global.u32 [%0], %1;" ::"l"(p), "r"(v) : "memory"); }
__device__ __forceinline__ uint32_t ld_rlx(const uint32_t* p) { uint32_t v; asm volatile("ld.relaxed.gpu.global.u32 %0, [%1];" : "=r"(v) : "l"(p) : "memory"); return v; }
__device__ __forceinline__ uint4 ld_rlx4(const void* p) { uint4 v; asm volatile("ld.relaxed.gpu.global.v4.u32 {%0,%1,%2,%3}, [%4];" : "=r"(v.x), "=r"(v.y), "=r"(v.z), "=r"(v.w) : "l"(p) : "memory"); return v; }
__device__ __forceinline__ float2 ld_rlx2f(const void* p) { float2 v; asm volatile("ld.relaxed.gpu.global.v2.f32 {%0,%1}, [%2];" : "=f"(v.x), "=f"(v.y) : "l"(p) : "memory"); return v; }
__device__ __forceinline__ void st_rlx4(void* p, uint4 v) { asm volatile("st.relaxed.gpu.global.v4.u32 [%0], {%1,%2,%3,%4};" ::"l"(p), "r"(v.x), "r"(v.y), "r"(v.z), "r"(v.w) : "memory"); }
__device__ __forceinline__ uint4 ldg_nc4(const void* p) { uint4 v; asm volatile("ld.global.nc.L1::no_allocate.v4.u32 {%0,%1,%2,%3}, [%4];" : "=r"(v.x), "=r"(v.y), "=r"(v.z), "=r"(v.w) : "l"(p)); return v; }
__device__ __forceinline__ uint32_t ldg_nc1(const void* p) { uint32_t v; asm volatile("ld.global.nc.u32 %0, [%1];" : "=r"(v) : "l"(p)); return v; }
__device__ __forceinline__ uint2 ld_rlx2(const void* p) { uint2 v; asm volatile("ld.relaxed.gpu.global.v2.u32 {%0,%1}, [%2];" : "=r"(v.x), "=r"(v.y) : "l"(p) : "memory"); return v; }
__device__ __forceinline__ void st_flag_if(uint32_t* p, uint32_t v, bool on) { asm volatile("{.reg .pred p; setp.ne.u32 p, %2, 0; @p st.relaxed.gpu.global.u32 [%0], %1;}" ::"l"(p), "r"(v), "r"((uint32_t)on) : "memory"); }
__device__ __forceinline__ void st_tag_if(uint2* p, float v, uint32_t tag, bool on) { asm volatile("{.reg .pred p; setp.ne.u32 p, %3, 0; @p st.relaxed.gpu.global.v2.u32 [%0], {%1,%2};}" ::"l"(p), "r"(__float_as_uint(v)), "r"(tag), "r"((uint32_t)on) : "memory"); }
__device__ __forceinline__ void stg1(void* p, uint32_t v) { asm volatile("st.global.u32 [%0], %1;" ::"l"(p), "r"(v)); }
__device__ __forceinline__ void poll_flags(const uint32_t* q, uint32_t v) {
  int it = 0;
  while (!__all_sync(0xffffffffu, (int)(ld_rlx(q) - v) >= 0)) { if (++it > (1 << 21)) asm volatile("trap;"); }
  asm volatile("fence.acquire.gpu;" ::: "memory");
  fence_async_gmem();
}
template <int N, bool YW>
__device__ __forceinline__ void poll_units(const uint4* const (&p)[N], uint4 (&v)[N], uint32_t epoch) {
  int it = 0;
  while (true) {
    uint32_t bad = 0;
#pragma unroll
    for (int q = 0; q < N; q++) v[q] = ld_rlx4(p[q]);
#pragma unroll
    for (int q = 0; q < N; q++) bad |= (v[q].w ^ epoch) | ((YW ? v[q].y : v[q].z) ^ epoch);
    if (__all_sync(0xffffffffu, bad == 0)) break;
    if (++it > (1 << 20)) asm volatile("trap;");
  }
}
__device__ __forceinline__ uint32_t lds1(uint32_t a) { uint32_t v; asm volatile("ld.shared.u32 %0, [%1];" : "=r"(v) : "r"(a)); return v; }
__device__ __forceinline__ void sts1_if(uint32_t a, uint32_t x, bool on) { asm volatile("{.reg .pred p; setp.ne.u32 p, %2, 0; @p st.shared.u32 [%0], %1;}" ::"r"(a), "r"(x), "r"((uint32_t)on) : "memory"); }
__device__ __forceinline__ uint4 lds4(uint32_t a) { uint4 v; asm volatile("ld.shared.v4.u32 {%0,%1,%2,%3}, [%4];" : "=r"(v.x), "=r"(v.y), "=r"(v.z), "=r"(v.w) : "r"(a)); return v; }
__device__ __forceinline__ float4 lds4f(uint32_t a) { float4 v; asm volatile("ld.shared.v4.f32 {%0,%1,%2,%3}, [%4];" : "=f"(v.x), "=f"(v.y), "=f"(v.z), "=f"(v.w) : "r"(a)); return v; }
__device__ __forceinline__ float2 lds2f(uint32_t a) { float2 v; asm volatile("ld.shared.v2.f32 {%0,%1}, [%2];" : "=f"(v.x), "=f"(v.y) : "r"(a)); return v; }
__device__ __forceinline__ void sts4(uint32_t a, uint4 v) { asm volatile("st.shared.v4.u32 [%0], {%1,%2,%3,%4};" ::"r"(a), "r"(v.x), "r"(v.y), "r"(v.z), "r"(v.w) : "memory"); }
__device__ __forceinline__ void sts4f(uint32_t a, float x, float y, float z, float w) { asm volatile("st.shared.v4.f32 [%0], {%1,%2,%3,%4};" ::"r"(a), "f"(x), "f"(y), "f"(z), "f"(w) : "memory"); }
__device__ __forceinline__ void sts2f(uint32_t a, float x, float y) { asm volatile("st.shared.v2.f32 [%0], {%1,%2};" ::"r"(a), "f"(x), "f"(y) : "memory"); }
__device__ __forceinline__ void sts2(uint32_t a, uint32_t x, uint32_t y) { asm volatile("st.shared.v2.u32 [%0], {%1,%2};" ::"r"(a), "r"(x), "r"(y) : "memory"); }
__device__ __forceinline__ void sts2_if(uint32_t a, uint32_t x, uint32_t y, bool on) { asm volatile("{.reg .pred p; setp.ne.u32 p, %3, 0; @p st.shared.v2.u32 [%0], {%1,%2};}" ::"r"(a), "r"(x), "r"(y), "r"((uint32_t)on) : "memory"); }
__device__ __forceinline__ void stsm4(uint32_t a, uint32_t r0, uint32_t r1, uint32_t r2, uint32_t r3) {
  asm volatile("stmatrix.sync.aligned.m8n8.x4.shared.b16 [%0], {%1,%2,%3,%4};" ::"r"(a), "r"(r0), "r"(r1), "r"(r2), "r"(r3));
}
__device__ __forceinline__ void ldsm4(uint32_t a, uint32_t& r0, uint32_t& r1, uint32_t& r2, uint32_t& r3) {
  asm volatile("ldmatrix.sync.aligned.m8n8.x4.shared.b16 {%0,%1,%2,%3}, [%4];" : "=r"(r0), "=r"(r1), "=r"(r2), "=r"(r3) : "r"(a) : "memory");
}
__device__ __forceinline__ uint32_t pack(float lo, float hi) { uint32_t r; asm("cvt.rn.bf16x2.f32 %0, %1, %2;" : "=r"(r) : "f"(hi), "f"(lo)); return r; }
__device__ __forceinline__ float blo(uint32_t v) { return __uint_as_float(v << 16); }
__device__ __forceinline__ float bhi(uint32_t v) { return __uint_as_float(v & 0xffff0000u); }
__device__ __forceinline__ void wg_fence() { asm volatile("wgmma.fence.sync.aligned;" ::: "memory"); }
__device__ __forceinline__ void wg_commit() { asm volatile("wgmma.commit_group.sync.aligned;" ::: "memory"); }
template <int N> __device__ __forceinline__ void wg_wait() { asm volatile("wgmma.wait_group.sync.aligned %0;" ::"n"(N) : "memory"); }
template <int N> __device__ __forceinline__ void pin(float (&d)[N]) {
#pragma unroll
  for (int i = 0; i < N; i++) asm volatile("" : "+f"(d[i])::"memory");
}
__device__ __forceinline__ uint32_t dlo(uint32_t addr, uint32_t lbo) { return ((addr & 0x3ffff) >> 4) | ((lbo >> 4) << 16); }
__host__ __device__ constexpr uint32_t dhi(uint32_t sbo, uint32_t sw) { return (sbo >> 4) | (sw << 30); }
constexpr uint32_t H_SW = dhi(1024, 1);
constexpr uint32_t H_NS = dhi(256, 0);
__device__ __forceinline__ uint64_t mk(uint32_t lo, uint32_t hi) { uint64_t d; asm("mov.b64 %0, {%1, %2};" : "=l"(d) : "r"(lo), "r"(hi)); return d; }
__device__ __forceinline__ uint64_t mkv(uint32_t lo, uint32_t off, uint32_t hi) { uint64_t d; asm volatile("{.reg .b32 t; add.u32 t, %1, %2; mov.b64 %0, {t, %3};}" : "=l"(d) : "r"(lo), "r"(off), "r"(hi)); return d; }
__device__ __forceinline__ void wgmma_w(float (&d)[40], uint64_t da, uint64_t oa, uint64_t db, uint64_t ob, int sc) { wgmma_ss_n80<0, 1>(d, da, oa, db, ob, sc); }
__device__ __forceinline__ void wgmma_w(float (&d)[48], uint64_t da, uint64_t oa, uint64_t db, uint64_t ob, int sc) { wgmma_ss_n96<0, 1>(d, da, oa, db, ob, sc); }
__device__ __forceinline__ float rcp(float x) { float r; asm("rcp.approx.ftz.f32 %0, %1;" : "=f"(r) : "f"(x)); return r; }
__device__ __forceinline__ float phi_h(float h) {
  float e;
  asm("ex2.approx.ftz.f32 %0, %1;" : "=f"(e) : "f"(fmaf(h, 2.8853900818f, -1.4426950409e-6f)));
  return (h + fabsf(h)) + __saturatef(e + 1e-6f);
}
__device__ __forceinline__ float gelu_h(float h) {
  float t;
  asm("tanh.approx.f32 %0, %1;" : "=f"(t) : "f"(h * fmaf(h * h, 0.2854192651f, 1.5957691216f)));
  return fmaf(h, t, h);
}

__device__ __forceinline__ uint32_t tagged(uint32_t v, uint32_t par, int l7, int pos) {
  const uint32_t m = l7 == pos ? 1u : 0u;
  return (v & ~m) | (par & m);
}
__device__ __forceinline__ uint32_t tag_off(int lane) { return (lane >> 4) * 2048 + ((lane >> 2) & 3) * 128 + (lane & 3) * 32 + (lane >> 2) * 4; }
template <bool G, int NR, class Init>
__device__ __forceinline__ void check_rows(uint32_t bad, uint32_t par, float (&acc)[NR], Init init, const unsigned char* a, const __nv_bfloat16* w, int ld, int cM, int cR, int lane) {
  if (__any_sync(0xffffffffu, bad & 1)) {
    REPAIR_CNT;
#pragma unroll 1
    for (int u = 0; u < (G ? 48 : 20); u++) {
      int it = 0;
      while (__any_sync(0xffffffffu, (ld_rlx(reinterpret_cast<const uint32_t*>(a + u * 4096 + tag_off(lane))) ^ par) & 1)) { if (++it > (1 << 20)) asm volatile("trap;"); }
    }
    float tmp[NR];
#pragma unroll 1
    for (int g = 0; g < NR / 4; g++) {
      float s0 = 0.f, s1 = 0.f, s2 = 0.f, s3 = 0.f;
#pragma unroll 1
      for (int k = 0; k < (G ? 1536 : 640); k += 2) {
        int kw = k;
        if (G) { const int pc = k >> 8, j = (k >> 5) & 7; kw = (pc / 3) * 768 + j * 96 + ((pc % 3 + (j & 1)) % 3) * 32 + (k & 31); }
        const uint32_t* pa = reinterpret_cast<const uint32_t*>(a + (k >> 4) * 2048 + (k & 8) * 16 + (lane >> 2) * 16 + (k & 7) * 2);
        const __nv_bfloat16* pw = w + (size_t)kw * ld + (g < 8 ? cM + g * 8 : cR + (g - 8) * 8) + (lane & 3) * 2;
        const uint32_t w0 = ldg_nc1(pw), w1 = ldg_nc1(pw + ld);
        const uint32_t a0 = ld_rlx(pa), a1 = ld_rlx(pa + 64);
        s0 = fmaf(blo(a0), blo(w0), fmaf(bhi(a0), blo(w1), s0));
        s1 = fmaf(blo(a0), bhi(w0), fmaf(bhi(a0), bhi(w1), s1));
        s2 = fmaf(blo(a1), blo(w0), fmaf(bhi(a1), blo(w1), s2));
        s3 = fmaf(blo(a1), bhi(w0), fmaf(bhi(a1), bhi(w1), s3));
      }
      tmp[4 * g] = s0; tmp[4 * g + 1] = s1; tmp[4 * g + 2] = s2; tmp[4 * g + 3] = s3;
    }
    init();
#pragma unroll
    for (int q = 0; q < NR; q++) acc[q] += tmp[q];
  }
}

template <bool MMA>
__device__ __forceinline__ void colsum_cta(const Params& P, uint32_t sm, int c, int warp, int lane, uint32_t epoch) {
  constexpr int NSL = 14;
  const uint32_t bar = sm + SM_BAR, ones = sm + SM_ROW;
  auto atom = [&](int a) { return a < 6 ? 34 + c * 5 + min(a, 4) : min(((a - 6) >> 1) * 8 + c * 2 + (a & 1), 33); };
  if (!MMA && warp == 8) {
    Ring r;
    r.ph = 1;
#pragma unroll 1
    for (int n = -6; n < (c ? 40 : 50); n++) {
      const int a = n < 0 ? n + 6 : 6 + (n / 10) * 2 + (n & 1), at = atom(a);
      const bool w1 = at >= 10 && at < 34;
      mbar_wait(bar + 8 * (B_E + r.s), r.ph);
      if (elect_one()) {
        mbar_expect(bar + 8 * (B_F + r.s), 16384);
        tma_ld(sm + r.s * 16384, w1 ? &P.w1S : &P.qkvS, (at < 10 ? at : (w1 ? at - 10 : at - 24)) * 64, n < 0 ? 512 : ((n % 10) >> 1) * 128, bar + 8 * (B_F + r.s));
        if (n >= 10 && n < 20) l2_prefetch(P.pwo + (c * 10 + n - 10) * 10240, 20480);
        if (n >= 20 && n < 40) l2_prefetch(P.pw2 + (c * 20 + n - 20) * 12288, 24576);
      }
      __syncwarp();
      r.next<NSL>();
    }
  } else if (!MMA) {
    if (warp < 11) {
      const int j = c * 2 + warp - 9;
#pragma unroll 1
      for (int q = lane; q < 560; q += 32) st_rlx4(reinterpret_cast<uint4*>(g_kv) + j * 560 + q, make_uint4(0, 0, 0, 0));
      __syncwarp();
      asm volatile("fence.acq_rel.gpu;" ::: "memory");
      st_flag_if(g_s.zflag + j * 8 + (lane & 7), ld_rlx(g_s.epoch) + 1, lane < 8);
    }
  } else {
    const int wg = warp >> 2;
    sts2(ones + lane * 8, 0x3f803f80u, 0x3f803f80u);
    fence_async_smem();
    bar_sync(1, 256);
    Ring r;
    r.s = wg;
    const uint32_t db = dlo(ones, 128);
#pragma unroll 1
    for (int a = wg; a < (c ? 14 : 16); a += 2) {
      float d[4];
      uint32_t pE = 0;
#pragma unroll 1
      for (int q = 0; q < (a < 6 ? 1 : 5); q++) {
        const uint32_t da = dlo(sm, 8192) + r.s * 1024;
        mbar_wait(bar + 8 * (B_F + r.s), r.ph);
        wg_fence();
#pragma unroll
        for (int kk = 0; kk < 8; kk++) wgmma_ss_n8<1, 0>(d, mk(da, H_SW), kk * 128, mk(db, dhi(128, 0)), 0, q | kk);
        wg_commit();
        wg_wait<1>();
        mbar_arrive_if(pE, q > 0 && lane == 0);
        pE = bar + 8 * (B_E + r.s);
        r.s += 2;
        if (r.s >= NSL) { r.s -= NSL; r.ph ^= 1; }
      }
      wg_wait<0>();
      pin(d);
      mbar_arrive_if(pE, lane == 0);
      if ((warp & 3) == 0) TS(a);
      st_tag_if(g_cs + atom(a) * 64 + (warp & 3) * 16 + (lane >> 2) + (lane & 1) * 8, (lane & 1) ? d[2] : d[0], epoch, (lane & 3) < 2);
    }
  }
}

template <int ROT>
__global__ void __launch_bounds__(512, 1) fused_block_kernel(const __grid_constant__ Params P) {
  extern __shared__ __align__(1024) unsigned char smem_raw[];
  const uint32_t sm = (uint32_t)__cvta_generic_to_shared(smem_raw);
  const uint32_t bar = sm + SM_BAR;
  const int tid = threadIdx.x, lane = tid & 31;
  const int warp = __shfl_sync(0xffffffffu, tid >> 5, 0);
  const int bx = ROT ? (blockIdx.x + ROT) % 132 : blockIdx.x;
  const bool spare = bx >= 128;
  const int rank = bx & 1, cl = bx >> 1, tq = cl - 4;
  const int bi = 2 * (cl < 4 ? 0 : (tq < 32 ? tq & 7 : 1 + (tq - 32) % 7)) + rank;
  const int bj = cl < 4 ? 4 + cl : (tq < 32 ? tq >> 3 : 4 + (tq - 32) / 7);
  const int b = bi * 8 + bj;
  if (warp == 8) { TS(63); TSG(46); }
  if (elect_one()) {
    if (warp == 8) {
      if (spare) asm volatile("prefetch.tensormap [%0];" ::"l"(&P.qkvS) : "memory");
#pragma unroll
      for (int k = 0; k < 3; k++) asm volatile("prefetch.tensormap [%0];" ::"l"(&P.x + k) : "memory");
    } else if (warp != 9) {
      if (warp < 7) {
        mbar_init(bar + 8 * (B_F + warp), 1);
        mbar_init(bar + 8 * (B_E + warp), spare ? 4 : 16);
        mbar_init(bar + 8 * (B_EA + warp), spare ? 4 : 8);
        if (spare) mbar_init(bar + 8 * (B_F + 7 + warp), 1);
        mbar_arrive_if(bar + 8 * (B_F + warp), !spare && (warp < 4 || warp == 6));
        mbar_arrive_n_if(bar + 8 * (B_E + warp), 16, !spare && warp < 4);
        mbar_arrive_n_if(bar + 8 * (B_EA + warp), 8, !spare && warp < 4);
      } else if (warp == 7) {
        mbar_init(bar + 8 * B_STAT1, 7); mbar_init(bar + 8 * B_STATQ, 1); mbar_init(bar + 8 * B_STAT2, 6); mbar_init(bar + 8 * B_KVP, 8);
      } else {
        mbar_init(bar + 8 * (B_GST + warp - 10), 8); mbar_init(bar + 8 * (B_GRDY + warp - 10), 1);
        if (warp < 15) mbar_init(bar + 8 * (B_KVB + warp - 10), warp == 10 ? 3 : 1);
      }
      asm volatile("fence.mbarrier_init.release.cluster;" ::: "memory");
      fence_async_smem();
    }
  }
  __syncwarp();
  asm volatile("barrier.cluster.arrive.relaxed.aligned;\n barrier.cluster.wait.aligned;" ::: "memory");

  uint32_t* const flags = g_flag + bi * 128;
  const int kb0 = (ABL & 32) ? 0 : bi >> 1;

  if (warp >= 8) {
    asm volatile("setmaxnreg.dec.sync.aligned.u32 72;");
    if (spare) {
      colsum_cta<false>(P, sm, bx - 128, warp, lane, 0);
    } else if (warp == 8) {
      TS(62);
      Ring r;
      r.s = 4; r.ph = 1;
      const uint32_t dB = sm + SM_B + rank * 4096;
      auto load_w = [&](const CUtensorMap* tm, int cM, int cR, int row, uint32_t bytes) {
        const uint32_t f = bar + 8 * (B_F + r.s), d = dB + r.s * 32768;
        mbar_wait(bar + 8 * (B_E + r.s), r.ph);
        if (elect_one()) {
          if (bytes) mbar_expect(f, bytes);
          tma_ld_mc(d, tm, cM, row, f);
          tma_ld_mc(d + 8192, tm + 1, cR, row, f);
        }
      };
      auto load_x = [&](uint32_t slot, int col) {
        if (elect_one()) tma_ld(sm + SM_A + slot * 32768, &P.x, col, bi * 128, bar + 8 * (B_F + r.s));
      };
      const int cq = bj * 80, r0 = rank * 32;
      int k = kb0 * 64;
#pragma unroll 1
      for (int it = 0; it < 10; it++) {
        load_w(&P.qkvM, cq + 640, cq + 704, k + r0, 26624);
        load_x(r.s >> 1, k);
        r.s++;
        load_w(&P.qkvM, cq + 1280, cq + 1344, k + r0, 10240);
        r.next<NS>();
        if (it == SLAB_AT) {
          if (elect_one()) {
            mbar_expect(bar + 8 * B_SLAB, (ABL & 16) ? 0 : 20480);
            if (!(ABL & 16)) bulk_ld(sm + SM_ST, P.px + (size_t)(bi * 128 + bj * 16) * 640, 20480, bar + 8 * B_SLAB);
          }
        }
        mbar_arrive_if(bar + 8 * B_LATE, it == LATE_AT && lane == 0);
        k = k == 576 ? 0 : k + 64;
      }
      k = k >= 192 ? k - 192 : k + 448;
#pragma unroll 1
      for (int it = 0; it < 3; it++) { load_w(&P.qkvM, cq, cq + 64, k + r0, 10240); r.s++; k = k == 576 ? 0 : k + 64; }
#pragma unroll 1
      for (int it = 0; it < 7; it++) {
        load_w(&P.qkvM, cq, cq + 64, k + r0, 26624);
        mbar_arrive_if(bar + 8 * B_KVEND, it == 0 && lane == 0);
        if (it == 2) {
          if (elect_one()) {
#pragma unroll
            for (int q = 3; q < 11; q++) asm volatile("prefetch.tensormap [%0];" ::"l"(&P.x + q) : "memory");
          }
          mbar_wait(bar + 8 * B_KVP, 0);
        }
        load_x(r.s, k);
        r.next<NS>();
        k = k == 576 ? 0 : k + 64;
      }
      const int cM = bj * 64, cR = 512 + bj * 16;
#pragma unroll 1
      for (k = r0; k < 640; k += 64) { load_w(&P.woM, cM, cR, k, 0); r.next<NS2>(); }
      {
        int c1 = bj * 96 + (bj & 1) * 32, c2 = bj * 96 + 64 - (bj & 1) * 64;
#pragma unroll 1
        for (k = r0; k < 640; k += 64) { load_w(&P.w1M, c1, c2, k, 0); r.next<NS2>(); }
        c1 += 768; c2 += 768;
        k = r0 + 192;
#pragma unroll 1
        for (int it = 0; it < 10; it++) { load_w(&P.w1M, c1, c2, k, 0); r.next<NS2>(); k = k >= 576 ? r0 : k + 64; }
      }
#pragma unroll 1
      for (int pc = 0; pc < 6; pc++) {
        k = (rank ? 0x1b1d1c030504ull : 0x1a1918020100ull) >> (8 * pc) & 0xff;
#pragma unroll 1
        for (int t = k * 32; t < k * 32 + 768; t += 192) { load_w(&P.w2M, cM, cR, t, 0); r.next<NS2>(); }
      }
    } else if (warp >= 12) {
      const uint32_t epoch = ld_rlx(g_s.epoch) + 1;
      const int w = warp - 12, r = w * 4 + (lane >> 3);
      float s = 0.f, ss = 0.f;
      uint32_t a = sm + SM_ST + r * 1280 + (lane & 7) * 16;
      mbar_wait(bar + 8 * B_SLAB, 0);
      if (w == 0) TS(53);
      uint4 v = lds4(a);
#pragma unroll 1
      for (int k = 0; k < ((ABL & 1) ? 0 : 10); k++) {
        a += 128;
        const uint4 u = lds4(a);
        float t;
        t = blo(v.x); s += t; ss = fmaf(t, t, ss); t = bhi(v.x); s += t; ss = fmaf(t, t, ss);
        t = blo(v.y); s += t; ss = fmaf(t, t, ss); t = bhi(v.y); s += t; ss = fmaf(t, t, ss);
        t = blo(v.z); s += t; ss = fmaf(t, t, ss); t = bhi(v.z); s += t; ss = fmaf(t, t, ss);
        t = blo(v.w); s += t; ss = fmaf(t, t, ss); t = bhi(v.w); s += t; ss = fmaf(t, t, ss);
        v = u;
      }
      if (w == 0) TS(48);
#pragma unroll
      for (int m = 1; m < 8; m <<= 1) { s += __shfl_xor_sync(0xffffffffu, s, m); ss += __shfl_xor_sync(0xffffffffu, ss, m); }
      const float mean = s * (1.f / 640.f);
      const float rstd = rsqrtf(fmaxf(ss * (1.f / 640.f) - mean * mean, 0.f) + 1e-5f);
      if (!(lane & 7)) st_rlx4(g_rs + bi * 128 + bj * 16 + r, make_uint4(__float_as_uint(rstd), __float_as_uint(-mean), epoch, epoch));
      __syncwarp();
      mbar_wait(bar + 8 * B_LATE, 0);
      {
        const uint4* const p[1] = {g_rs + bi * 128 + w * 32 + lane};
        uint4 v1[1];
        if (ABL & 2) v1[0] = make_uint4(0, 0, 0, 0); else poll_units<1, false>(p, v1, epoch);
        sts2(sm + SM_ROW + (w * 32 + lane) * 8, v1[0].x, v1[0].y);
      }
      __syncwarp();
      mbar_arrive_if(bar + 8 * B_STAT1, lane == 0);
      if (w == 0) TS(49);
      if (w == 0) {
        mbar_wait(bar + 8 * B_KVEND, 0);
        const uint4* const p[2] = {reinterpret_cast<const uint4*>(g_cs + bj * 80) + lane, reinterpret_cast<const uint4*>(g_cs + bj * 80) + 32 + (lane & 7)};
        uint4 v2[2];
        poll_units<2, true>(p, v2, epoch);
        sts2(sm + SM_COL + lane * 8, v2[0].x, v2[0].z);
        sts2(sm + SM_COL + (32 + (lane & 7)) * 8, v2[1].x, v2[1].z);
        __syncwarp();
        mbar_arrive_if(bar + 8 * B_STATQ, lane == 0);
      }
      {
        mbar_wait(bar + 8 * B_HSEEN, 0);
        const uint4* p[8]; uint4 v8[8];
#pragma unroll
        for (int jj = 0; jj < 8; jj++) p[jj] = g_hstat + (bi * 8 + jj) * 128 + w * 32 + lane;
        poll_units<8, false>(p, v8, epoch);
        float s2 = 0.f, q2 = 0.f;
#pragma unroll
        for (int jj = 0; jj < 8; jj++) { s2 += __uint_as_float(v8[jj].x); q2 += __uint_as_float(v8[jj].y); }
        const float m2 = s2 * (1.f / 640.f);
        const float rs2 = 0.5f * rsqrtf(fmaxf(q2 * (1.f / 640.f) - m2 * m2, 0.f) + 1e-5f);
        sts2f(sm + SM_ROW + (w * 32 + lane) * 8, rs2, -m2 * rs2);
        __syncwarp();
        mbar_arrive_if(bar + 8 * B_STAT2, lane == 0);
        if (w == 0) TS(44);
      }
    } else {
      const uint32_t epoch = ld_rlx(g_s.epoch) + 1;
      const int hl = tid - 288;
      uint32_t dst[6];
#pragma unroll
      for (int q = 0; q < 6; q++) {
        uint32_t t[2];
#pragma unroll
        for (int h = 0; h < 2; h++) {
          const int u = q * 96 + hl, pr = min((u >> 1) * 3 + (u & 1) * 2 + h, 839), row = pr / 10, hh = row / 21, e = row - hh * 21;
          const int hf = hh >> 1, h1 = hh & 1, k = h1 * 20 + (pr - row * 10) * 2 + hf * 8, n = e < 20 ? h1 * 20 + e : 40 + h1;
          t[h] = (hf * 4608 + (k >> 3) * 128 + (k & 7) * 2 + (n >> 3) * 768 + (n & 7) * 16) | (e < 20 ? 0u : 0x8000u);
        }
        dst[q] = t[0] | (t[1] << 16);
        asm volatile("" : "+r"(dst[q]));
      }
      {
        mbar_wait(bar + 8 * B_LATE, 0);
        const int u = min(hl, 79);
        const uint4* p[9]; uint4 v[9];
#pragma unroll
        for (int g = 0; g < 8; g++) p[g] = reinterpret_cast<const uint4*>(g_cp + (bj * 8 + g) * 160) + u;
        p[8] = reinterpret_cast<const uint4*>(g_cs + 2176 + (u >= 40 ? 560 : 0) + bj * 80) + u;
        if (ABL & 4) { for (int g = 0; g < 9; g++) v[g] = make_uint4(0, 0, 0, 0); } else poll_units<9, true>(p, v, epoch);
        float s0 = 0.f, s1 = 0.f;
#pragma unroll
        for (int g = 0; g < 9; g++) { s0 += __uint_as_float(v[g].x); s1 += __uint_as_float(v[g].z); }
        sts2f(sm + SM_COL + 320 + u * 8, s0, s1);
        __syncwarp();
        mbar_arrive_if(bar + 8 * B_STAT1, lane == 0);
      }
      if (warp == 9) {
        TS(52);
        poll_flags(g_s.zflag + bj * 8, epoch);
        mbar_wait(bar + 8 * B_KVP, 0);
        if (elect_one()) {
          bulk_red_f32(g_kv + bj * 2240, sm + SM_PK, 4480);
          bulk_red_f32(g_kv + bj * 2240 + 1120, sm + SM_PK + 10240, 4480);
          bulk_commit();
        }
        __syncwarp();
        TS(50);
      } else {
        const int w = warp - 10;
        mbar_wait(bar + 8 * B_KVP, 0);
#pragma unroll
        for (int q = 0; q < 9; q++) sts4(sm + SM_KVB + (q * 64 + w * 32 + lane) * 16, make_uint4(0, 0, 0, 0));
      }
      bar_sync(3, 96);
      {
        uint4 v[6];
        const uint4* src = reinterpret_cast<const uint4*>(g_kv + bj * 2240) + hl;
        const int last = hl < 80 ? 480 : 0;
        int it = 0;
        while (ld_rlx(reinterpret_cast<const uint32_t*>(g_kv + bj * 2240) + 2239 - (warp - 9) * 32) != 0x41800000u) { if (++it > (1 << 20)) asm volatile("trap;"); }
        while (true) {
          uint32_t bad = 0;
#pragma unroll
          for (int q = 0; q < 6; q++) v[q] = ld_rlx4(src + (q < 5 ? q * 96 : last));
#pragma unroll
          for (int q = 0; q < 6; q++) bad |= v[q].w ^ 0x41800000u;
          if (__all_sync(0xffffffffu, bad == 0 || !(lane & 1))) break;
          if (++it > (1 << 20)) asm volatile("trap;");
        }
        if (warp == 9) TS(54);
        {
          uint32_t e6;
          asm("mapa.shared::cluster.u32 %0, %1, %2;" : "=r"(e6) : "r"(bar + 8 * (B_E + 6)), "r"(lane & 1));
          mbar_arrive_cl_if(e6, warp == 11 ? 2 : 3, lane < 2);
        }
#pragma unroll
        for (int q = 0; q < 6; q++) {
          const uint32_t lo = pack(__uint_as_float(v[q].x), __uint_as_float(v[q].y)), hi = pack(__uint_as_float(v[q].z), __uint_as_float(v[q].w));
          const uint32_t a0 = sm + SM_KVB + (dst[q] & 0x7fffu), a1 = sm + SM_KVB + ((dst[q] >> 16) & 0x7fffu);
          const bool on0 = q < 5 || hl < 80, on1 = on0 && !(lane & 1), z0 = on0 && (dst[q] & 0x8000u), z1 = on1 && (dst[q] >> 31);
          sts1_if(a0, lo, on0);
          sts1_if(a1, hi, on1);
          if (q == 1 || q == 2 || q >= 4) {
#pragma unroll
            for (int rep = 1; rep < 4; rep++) { sts1_if(a0 + rep * 32, lo, z0); sts1_if(a1 + rep * 32, hi, z1); }
          }
        }
        fence_async_smem();
        __syncwarp();
        mbar_arrive_if(bar + 8 * B_KVB, lane == 0);
      }
      if (warp == 9) {
        TS(55);
        Ring r;
        r.s = 4; r.ph = 1;
        auto load_a = [&](const unsigned char* src, uint32_t half, uint32_t bytes) {
          const uint32_t f = bar + 8 * (B_F + r.s), d = sm + SM_A + r.s * 32768;
          mbar_wait(bar + 8 * (B_EA + r.s), r.ph);
          if (elect_one()) {
            mbar_expect(f, bytes);
            bulk_ld(d, src, 8192, f);
            bulk_ld(d + 8192, src + half, 8192, f);
          }
        };
#pragma unroll 1
        for (int ph = 0; ph < 3; ph++) {
          const unsigned char* src = (ph ? g_h : g_o) + (size_t)bi * 163840;
          if (ph < 2) {
            poll_flags(flags + (lane & 15) * 8, epoch * 8 + ph);
            TS(32 + ph);
          } else {
#pragma unroll 1
            for (int n = NS2; n > 0; n--) {
              mbar_wait(bar + 8 * (B_EA + r.s), r.ph);
              if (elect_one()) mbar_expect(bar + 8 * (B_F + r.s), 12288);
              r.next<NS2>();
            }
          }
#pragma unroll 1
          for (int n = ph < 2 ? 10 : 10 - NS2; n > 0; n--) {
            load_a(src, 81920, ph ? 28672 : 26624); src += 8192; r.next<NS2>();
            mbar_arrive_if(bar + 8 * B_HSEEN, ph == 1 && n == 4 && lane == 0);
          }
        }
        const unsigned char* src = g_g + (size_t)bi * 393216;
#pragma unroll 1
        for (int pc = 0; pc < 6; pc++) {
          mbar_wait(bar + 8 * (B_GRDY + pc), 0);
          TS(36 + pc);
#pragma unroll 1
          for (int n = 4; n > 0; n--) { load_a(src, 196608, 26624); src += 8192; r.next<NS2>(); }
        }
      } else {
        const int w = warp - 10;
        {
          const uint4* p[2]; uint4 v[2]; uint32_t bb[2];
#pragma unroll
          for (int q = 0; q < 2; q++) {
            const int n = 2 * (q ? 32 + (lane & 15) : lane);
            const int col = w * 768 + bj * 96 + ((bj & 1) ? (q ? n - 64 : n + 32) : n);
            p[q] = reinterpret_cast<const uint4*>(g_cs + 640 + col);
            bb[q] = ldg_nc1(P.pb1 + col);
          }
          mbar_wait(bar + 8 * B_HSEEN, 0);
          poll_units<2, true>(p, v, epoch);
#pragma unroll
          for (int q = 0; q < 2; q++)
            sts4f(sm + SM_COL + w * 768 + (q ? 32 + (lane & 15) : lane) * 16, __uint_as_float(v[q].x), __uint_as_float(v[q].z), 0.5f * blo(bb[q]), 0.5f * bhi(bb[q]));
        }
        __syncwarp();
        mbar_arrive_if(bar + 8 * B_STAT2, lane == 0);
#pragma unroll 1
        for (int q = w; q < 6; q += 2) {
          mbar_wait(bar + 8 * (B_GST + q), 0);
          st_flag_if(flags + (w * 8 + bj) * 8 + (lane & 7), epoch * 8 + 2 + q, lane < 8);
          TS(56 + q);
          poll_flags(flags + (w * 8 + (lane & 7)) * 8, epoch * 8 + 2 + q);
          TS(q < 2 ? 34 + q : (q < 4 ? 40 + q : (q == 4 ? 45 : 51)));
          mbar_arrive_if(bar + 8 * (B_GRDY + q), lane == 0);
        }
      }
    }
  } else {
    asm volatile("setmaxnreg.inc.sync.aligned.u32 184;");
    const uint32_t epoch = ld_rlx(g_s.epoch) + 1;
    if (spare) { colsum_cta<true>(P, sm, bx - 128, warp, lane, epoch); return; }
    const int wg = warp >> 2, w4 = warp & 3, qr = lane >> 2, qc = lane & 3;
    const uint32_t ra = sm + SM_A + wg * 8192, bF = bar + 8 * B_F;
    uint32_t bE;
    asm("mapa.shared::cluster.u32 %0, %1, %2;" : "=r"(bE) : "r"(bar + 8 * B_E), "r"(lane & 1));
    Ring r;
    r.s = 4;
    const uint32_t rowst = sm + SM_ROW + (wg * 64 + w4 * 16 + qr) * 8;
    const uint32_t xoff = w4 * 512 + lane * 4;
    const uint32_t dW = dlo(sm + SM_B, 8192), dX = dlo(ra, 16), dA = dlo(ra, 128);
    uint32_t pq[20], hres[20];

    uint32_t bE3 = lane == 2 ? bar + 8 * B_EA : bE, rel2 = lane < 2, rel3 = lane < 3;
    uint32_t par = epoch, chk = ra + w4 * 512 + tag_off(lane);
    asm volatile("" : "+r"(bE3), "+r"(chk), "+r"(rel2), "+r"(rel3));
    const int l7 = lane & 7;
    uint32_t bad = 0, c0 = par, c1 = par;
    auto fold = [&]() { uint32_t t; asm("lop3.b32 %0, %1, %2, %3, 0x7e;" : "=r"(t) : "r"(c0), "r"(c1), "r"(par)); bad |= t; };
    auto gemm = [&](auto sw, auto& acc, uint32_t sc, int tsb, int nblk, uint32_t rel, uint32_t rnext, uint32_t pE) {
      constexpr bool SW = decltype(sw)::value;
#pragma unroll 1
      for (; nblk > 0; nblk--) {
        const uint64_t da = mk((SW ? dX : dA) + r.s * 2048, SW ? H_SW : H_NS), db = mk(dW + r.s * 2048, H_SW);
        mbar_wait(bF + 8 * r.s, r.ph);
        TSB(tsb++);
        wg_fence();
#pragma unroll
        for (int kk = 0; kk < 4; kk++) wgmma_w(acc, da, kk * (SW ? 2 : 128), db, kk * 128, kk ? 1 : sc);
        wg_commit();
        if (!SW) fold();
        wg_wait<1>();
        mbar_arrive_cl1_if(pE, rel);
        if (!SW) { c0 = lds1(chk + r.s * 32768); c1 = lds1(chk + r.s * 32768 + 4096); }
        pE = bE3 + 8 * r.s;
        rel = rnext;
        sc = 1;
        r.next<SW ? NS : NS2>();
      }
    };
    auto drain = [&](auto sw, auto& acc) {
      constexpr bool SW = decltype(sw)::value;
      if (!SW) fold();
      wg_wait<0>();
      pin(acc);
      mbar_arrive_cl1_if(bE3 + 8 * r.prev<SW ? NS : NS2>(), SW ? rel2 : rel3);
    };
    auto announce = [&](int q) {
      bar_sync(4 + wg, 128);
      st_flag_if(flags + (wg * 8 + bj) * 8 + (lane & 7), epoch * 8 + q, w4 == 0 && lane < 8);
    };

    {
      float aK[40], aV[40];
      const uint32_t xrow = ra + (w4 * 16 + (lane & 15)) * 128;
      const uint32_t bE2 = bE + (lane >> 1) * 8;
      int k = kb0;
      float aC[40];
      uint32_t pa[5];
#pragma unroll
      for (int g = 0; g < 5; g++) {
        uint32_t t[2];
#pragma unroll
        for (int h = 0; h < 2; h++) {
          const int e = w4 * 16 + qr + h * 8 - wg * 8;
          const bool z = e == (wg ? -8 : 40);
          const int d = g * 4 + qc, hd = d >= 10, e1 = z ? 20 : e - 20 * hd;
          const int pr = (hd * 21 + e1) * 10 + d - 10 * hd, sec = (pr * 21846) >> 16;
          t[h] = (z || (e1 >= 0 && e1 < 20)) ? sec * 8 + pr * 8 : 0xffffu;
        }
        pa[g] = t[0] | (t[1] << 16);
        asm volatile("" : "+r"(pa[g]));
      }
      auto kv_step = [&](int it, auto mode) {
        constexpr int MODE = decltype(mode)::value;
        const uint64_t da = mk(dX + r.s * 1024, H_SW), db = mk(dW + r.s * 2048, H_SW);
        mbar_wait(bF + 8 * r.s, r.ph);
        if (MODE == 0) TSW(0);
        TSB(2 * it);
        wg_fence();
#pragma unroll
        for (int kk = 0; kk < 4; kk++) wgmma_w(aK, da, kk * 2, db, kk * 128, kk || MODE);
        wg_commit();
        if (MODE) {
          wg_wait<1>();
          mbar_arrive_cl1_if(bE2 + 8 * (r.prev<NS>() - 1), lane < 4);
        }
        if (MODE == 1 && wg == 0 && !(ABL & 8)) {
          pin(aC);
#pragma unroll
          for (int g = 0; g < 10; g++)
            st_rlx4_if(g_cp + (bj * 8 + kb0) * 160 + rank * 80 + g * 8 + qc * 2, __float_as_uint(aC[4 * g]), epoch, __float_as_uint(aC[4 * g + 1]), epoch, qr == 0 && w4 == (g & 3));
        }
        mbar_wait(bF + 8 * r.s + 8, r.ph);
        TSB(2 * it + 1);
        wg_fence();
#pragma unroll
        for (int kk = 0; kk < 4; kk++) wgmma_w(aV, da, kk * 2, db, 2048 + kk * 128, kk || MODE);
        if (MODE == 0 && wg == 0 && !(ABL & 8)) {
          wg_fence();
#pragma unroll
          for (int kk = 0; kk < 4; kk++) wgmma_rs_n80<1>(aC, 0x3f803f80u, 0x3f803f80u, 0x3f803f80u, 0x3f803f80u, db + rank * 2048, kk * 128, kk);
        }
        wg_commit();
        if (k == bj) {
#pragma unroll
          for (int u = 0; u < 4; u++) ldsm4(xrow + r.s * 16384 + (((2 * u + (lane >> 4)) ^ (lane & 7)) << 4), hres[4 * u], hres[4 * u + 1], hres[4 * u + 2], hres[4 * u + 3]);
        }
        if (k == 8 + (bj >> 2)) ldsm4(xrow + r.s * 16384 + (((2 * (bj & 3) + (lane >> 4)) ^ (lane & 7)) << 4), hres[16], hres[17], hres[18], hres[19]);
        r.next<NS>(); r.next<NS>();
        k = k == 9 ? 0 : k + 1;
      };
      kv_step(0, std::integral_constant<int, 0>{});
      kv_step(1, std::integral_constant<int, 1>{});
#pragma unroll 1
      for (int it = 2; it < 10; it++) kv_step(it, std::integral_constant<int, 2>{});
      mbar_wait(bar + 8 * B_STAT1, 0);
      const float2 r0 = lds2f(rowst), r1 = lds2f(rowst + 64);
      const float h0 = 0.5f * r0.x, h1 = 0.5f * r1.x;
      const uint32_t stg = (lane >> 4) * 2048 + (wg * 8 + w4 * 2 + ((lane >> 3) & 1)) * 128 + (lane & 7) * 16;
      float2 c[10], cv[10];
#pragma unroll
      for (int g = 0; g < 10; g++) { c[g] = lds2f(sm + SM_COL + (80 + g * 8 + qc * 2) * 4); cv[g] = lds2f(sm + SM_COL + (160 + g * 8 + qc * 2) * 4); }
      sts2(sm + SM_V + 10240 + tid * 8, 0x3f803f80u, 0x3f803f80u);
      wg_wait<1>();
      pin(aK);
      TSW(1);
#pragma unroll
      for (int u = 0; u < 5; u++) {
        uint32_t pk[4];
#pragma unroll
        for (int h = 0; h < 2; h++) {
          const int g = 2 * u + h;
          pk[2 * h] = pack(phi_h(fmaf(fmaf(r0.y, c[g].x, aK[4 * g]), h0, 0.5e-6f)), phi_h(fmaf(fmaf(r0.y, c[g].y, aK[4 * g + 1]), h0, 0.5e-6f)));
          pk[2 * h + 1] = pack(phi_h(fmaf(fmaf(r1.y, c[g].x, aK[4 * g + 2]), h1, 0.5e-6f)), phi_h(fmaf(fmaf(r1.y, c[g].y, aK[4 * g + 3]), h1, 0.5e-6f)));
        }
        stsm4(sm + SM_PK + u * 4096 + stg, pk[0], pk[1], pk[2], pk[3]);
        if (u == 1) {
          wg_wait<0>();
          pin(aV);
          mbar_arrive_cl1_if(bE2 + 8 * (r.prev<NS>() - 1), lane < 4);
        }
      }
#pragma unroll
      for (int u = 0; u < 5; u++) {
        uint32_t pv[4];
#pragma unroll
        for (int h = 0; h < 2; h++) {
          const int g = 2 * u + h;
          pv[2 * h] = pack(fmaf(r0.y, cv[g].x, aV[4 * g]) * r0.x, fmaf(r0.y, cv[g].y, aV[4 * g + 1]) * r0.x);
          pv[2 * h + 1] = pack(fmaf(r1.y, cv[g].x, aV[4 * g + 2]) * r1.x, fmaf(r1.y, cv[g].y, aV[4 * g + 3]) * r1.x);
        }
        const uint32_t skip = u > 2 ? 2048u : (u == 2 ? (uint32_t)(lane >> 4) * 2048u : 0u);
        stsm4(sm + SM_V + u * 4096 + skip + stg, pv[0], pv[1], pv[2], pv[3]);
      }
      fence_async_smem();
      mbar_wait(bar + 8 * B_STATQ, 0);
#pragma unroll
      for (int g = 0; g < 10; g++) c[g] = lds2f(sm + SM_COL + (g * 8 + qc * 2) * 4);
      bar_sync(1, 256);
      TSW(7);
      float aD[20];
      const uint32_t part = sm + SM_PK + wg * 10240;
      const uint32_t da = dlo(sm + SM_V + wg * 10240, 128), db = dlo(part, 128);
      wg_fence();
#pragma unroll
      for (int kk = 0; kk < 8; kk++) wgmma_ss_n40<1, 1>(aD, mk(da, dhi(2048, 0)), kk * 16, mk(db, dhi(2048, 0)), kk * 16, kk);
      wg_commit();
#pragma unroll
      for (int g = 0; g < 10; g++) { aK[4 * g] = r0.y * c[g].x; aK[4 * g + 1] = r0.y * c[g].y; aK[4 * g + 2] = r1.y * c[g].x; aK[4 * g + 3] = r1.y * c[g].y; }
      pin(aK);
      gemm(std::true_type{}, aK, 1, 20, 1, 0, 0, 0);
      pin(aD);
      bar_sync(4 + wg, 128);
#pragma unroll
      for (int h = 0; h < 2; h++)
#pragma unroll
        for (int g = 0; g < 5; g++) {
          const uint32_t o = (pa[g] >> (16 * h)) & 0xffffu;
          sts2_if(part + o, __float_as_uint(aD[4 * g + 2 * h]), __float_as_uint(aD[4 * g + 2 * h + 1]), o != 0xffffu);
        }
      sts2(part + (tid & 127) * 32 + 24, 0u, 0x3f800000u);
      sts2_if(part + (128 + (tid & 127)) * 32 + 24, 0u, 0x3f800000u, (tid & 127) < 12);
      fence_async_smem();
      __syncwarp();
      mbar_arrive_if(bar + 8 * B_KVP, lane == 0);
      TSW(2);
      gemm(std::true_type{}, aK, 1, 21, 9, rel2, rel2, bE3);
      drain(std::true_type{}, aK);
      TSW(3);
      auto phi_q = [&](int g) {
        pq[2 * g] = pack(phi_h(fmaf(aK[4 * g], h0, 0.5e-6f)), phi_h(fmaf(aK[4 * g + 1], h0, 0.5e-6f)));
        pq[2 * g + 1] = pack(phi_h(fmaf(aK[4 * g + 2], h1, 0.5e-6f)), phi_h(fmaf(aK[4 * g + 3], h1, 0.5e-6f)));
      };
      unsigned char* dst = g_o + (size_t)((bi * 2 + wg) * 40 + bj * 5) * 2048 + xoff;
      const int lo7 = l7 ^ ((bj & 1) * 4);
      auto send_o = [&](float (&a)[24], int G0) {
        float inv[4];
#pragma unroll
        for (int q = 0; q < 4; q++) inv[q] = rcp(a[20 + q] + 1e-6f);
#pragma unroll
        for (int g = 0; g < 5; g++) {
          const int G = G0 + g;
          const bool hd = g > 2 || (g == 2 && qc >= 2);
          const float i0 = hd ? inv[1] : inv[0], i1 = hd ? inv[3] : inv[2];
          stg1(dst + (G >> 1) * 2048 + (G & 1) * 128, tagged(pack(a[4 * g] * i0, a[4 * g + 1] * i0), par, lo7, (G & 2) * 2 + (G & 1)));
          stg1(dst + (G >> 1) * 2048 + (G & 1) * 128 + 256, tagged(pack(a[4 * g + 2] * i1, a[4 * g + 3] * i1), par, lo7, (G & 2) * 2 + (G & 1) + 2));
        }
      };
      float a0[24], a1[24];
      const uint64_t dk = mk(dlo(sm + SM_KVB, 128), dhi(768, 0));
#pragma unroll
      for (int g = 0; g < 6; g++) phi_q(g);
      mbar_wait(bar + 8 * B_KVB, 0);
      TSW(4);
      wg_fence();
#pragma unroll
      for (int kk = 0; kk < 3; kk++) wgmma_rs_n48<0>(a0, pq[4 * kk], pq[4 * kk + 1], pq[4 * kk + 2], pq[4 * kk + 3], dk, kk * 16, kk);
      wg_commit();
#pragma unroll
      for (int g = 6; g < 10; g++) phi_q(g);
      wg_fence();
#pragma unroll
      for (int kk = 0; kk < 3; kk++) wgmma_rs_n48<0>(a1, pq[4 * kk + 8], pq[4 * kk + 9], pq[4 * kk + 10], pq[4 * kk + 11], dk, 288 + kk * 16, kk);
      wg_commit();
      wg_wait<1>();
      pin(a0);
      send_o(a0, 0);
      wg_wait<0>();
      pin(a1);
      send_o(a1, 5);
      announce(0);
      TSW(5);
    }
    float accF[40];
    {
      auto init = [&]() {
#pragma unroll
        for (int q = 0; q < 20; q++) { accF[2 * q] = blo(hres[q]); accF[2 * q + 1] = bhi(hres[q]); }
      };
      init();
      uint32_t b2v[10];
#pragma unroll
      for (int g = 0; g < 10; g++) b2v[g] = ldg_nc1(P.pb2 + (g < 8 ? bj * 64 + g * 8 : 512 + bj * 16 + (g - 8) * 8) + qc * 2);
      pin(accF);
      gemm(std::false_type{}, accF, 1, 30, 10, 0, rel3, 0);
      drain(std::false_type{}, accF);
      check_rows<false>(bad, par, accF, init, g_o + (size_t)(bi * 2 + wg) * 81920 + w4 * 512, P.pwo, 640, bj * 64, 512 + bj * 16, lane);
      TSW(8);
      unsigned char* dst = g_h + (size_t)(bi * 2 + wg) * 81920 + xoff;
#pragma unroll
      for (int g = 0; g < 10; g++) {
        hres[2 * g] = pack(accF[4 * g], accF[4 * g + 1]);
        hres[2 * g + 1] = pack(accF[4 * g + 2], accF[4 * g + 3]);
        unsigned char* d = dst + (g < 8 ? bj * 8192 + (g >> 1) * 2048 : (32 + bj) * 2048) + (g & 1) * 128;
        const int lh7 = g < 8 ? l7 : l7 ^ ((bj & 1) * 4);
        stg1(d, tagged(hres[2 * g], par, lh7, (g & 2) * 2 + (g & 1)));
        stg1(d + 256, tagged(hres[2 * g + 1], par, lh7, (g & 2) * 2 + (g & 1) + 2));
      }
      announce(1);
      bad = 0; c0 = c1 = par;
      TSW(9);
      float s0 = 0.f, q0 = 0.f, s1 = 0.f, q1 = 0.f;
#pragma unroll
      for (int g = 0; g < 10; g++) {
        const float a = blo(hres[2 * g]), c = bhi(hres[2 * g]), d = blo(hres[2 * g + 1]), e = bhi(hres[2 * g + 1]);
        s0 += a + c; q0 = fmaf(a, a, fmaf(c, c, q0));
        s1 += d + e; q1 = fmaf(d, d, fmaf(e, e, q1));
        accF[4 * g] = a + blo(b2v[g]); accF[4 * g + 1] = c + bhi(b2v[g]);
        accF[4 * g + 2] = d + blo(b2v[g]); accF[4 * g + 3] = e + bhi(b2v[g]);
      }
#pragma unroll
      for (int m = 1; m < 4; m <<= 1) {
        s0 += __shfl_xor_sync(0xffffffffu, s0, m); q0 += __shfl_xor_sync(0xffffffffu, q0, m);
        s1 += __shfl_xor_sync(0xffffffffu, s1, m); q1 += __shfl_xor_sync(0xffffffffu, q1, m);
      }
      if (qc < 2) st_rlx4(g_hstat + b * 128 + wg * 64 + w4 * 16 + qr + qc * 8, make_uint4(__float_as_uint(qc ? s1 : s0), __float_as_uint(qc ? q1 : q0), epoch, epoch));
      __syncwarp();
      pin(accF);
    }
    {
      float accA[48], accB[48];
      float2 r0, r1;
      unsigned char* const dg = g_g + (size_t)(bi * 2 + wg) * 196608 + bj * 4096 + xoff;
      auto ready = [&](int n) { mbar_wait(bF + 8 * ((n - 26) % NS2), (1 + (n - 26) / NS2) & 1); };
      auto block = [&](auto& acc, int n, int sc) {
        const int s = (n - 26) % NS2;
        if (n < ALT_END) bar_sync(6 + wg, 256);
        TSB(n < 60 ? n + 24 : n - 10);
        wg_fence();
#pragma unroll
        for (int kk = 0; kk < 4; kk++) wgmma_w(acc, mkv(dA, s * 2048 + kk * 128, H_NS), 0, mkv(dW, s * 2048 + kk * 128, H_SW), 0, kk ? 1 : sc);
        wg_commit();
        if (n < ALT_END - 1 || (n == ALT_END - 1 && wg == 0)) bar_arrive(7 - wg, 256);
        if (n <= 50 || n > 50 + NS2) fold();
        wg_wait<1>();
        mbar_arrive_cl1_if(bE3 + 8 * ((n - 27) % NS2), rel3);
        if (n >= 50 + NS2) { c0 = lds1(chk + s * 32768); c1 = lds1(chk + s * 32768 + 4096); }
      };
      auto check = [&](float (&acc)[48], int ch) {
        pin(acc);
        check_rows<false>(bad, par, acc, [&]() {
#pragma unroll
          for (int q = 0; q < 48; q++) acc[q] = 0.f;
        }, g_h + (size_t)(bi * 2 + wg) * 81920 + w4 * 512, P.pw1, 1536, ch * 768 + bj * 96 + (bj & 1) * 32, ch * 768 + bj * 96 + 64 - (bj & 1) * 64, lane);
        if (ch) bad = 0;
      };
      float4 cn[2];
      auto gelu_fetch = [&](int ch, int g0, int g1) {
#pragma unroll
        for (int g = g0; g < g1; g++) cn[g - g0] = lds4f(sm + SM_COL + ch * 768 + qc * 16 + g * 64);
      };
      auto gelu_groups = [&](float (&acc)[48], int ch, int g0, int g1) {
#pragma unroll
        for (int g = g0; g < g1; g++) {
          const float4 c = cn[g - g0];
          asm volatile("" : "+f"(acc[4 * g]), "+f"(acc[4 * g + 1]), "+f"(acc[4 * g + 2]), "+f"(acc[4 * g + 3]));
          unsigned char* d = dg + (ch * 3 + (g >> 2)) * 32768 + ((g >> 1) & 1) * 2048 + (g & 1) * 128;
          const uint32_t y0 = pack(gelu_h(fmaf(acc[4 * g], r0.x, fmaf(r0.y, c.x, c.z))), gelu_h(fmaf(acc[4 * g + 1], r0.x, fmaf(r0.y, c.y, c.w))));
          const uint32_t y1 = pack(gelu_h(fmaf(acc[4 * g + 2], r1.x, fmaf(r1.y, c.x, c.z))), gelu_h(fmaf(acc[4 * g + 3], r1.x, fmaf(r1.y, c.y, c.w))));
          stg1(d, tagged(y0, par, l7, (g & 2) * 2 + (g & 1)));
          stg1(d + 256, tagged(y1, par, l7, (g & 2) * 2 + (g & 1) + 2));
          if ((g & 3) == 3) { __syncwarp(); mbar_arrive_if(bar + 8 * (B_GST + ch * 3 + (g >> 2)), lane == 0); }
        }
      };
      gemm(std::false_type{}, accA, 0, 40, 10, 0, rel3, 0);
      mbar_wait(bar + 8 * B_STAT2, 0);
      r0 = lds2f(rowst); r1 = lds2f(rowst + 64);
      if (ALT_END > 50 && wg == 1) bar_arrive(6, 256);
      TSW(10);
      ready(50);
#pragma unroll
      for (int t = 0; t < 10; t++) {
        block(accB, 50 + t, t);
        gelu_fetch(0, GA(t), GA(t + 1));
        if (t == 0) check(accA, 0);
        ready(51 + t);
        gelu_groups(accA, 0, GA(t), GA(t + 1));
      }
      TSW(12);
#pragma unroll
      for (int t = 0; t < GBN; t++) {
        block(accF, 60 + t, 1);
        gelu_fetch(1, GB(t), GB(t + 1));
        if (t == 0) check(accB, 1);
        ready(61 + t);
        gelu_groups(accB, 1, GB(t), GB(t + 1));
      }
      block(accF, 60 + GBN, 1);
      TSW(13);
      r.s = (35 + GBN) % NS2; r.ph = (1 + (35 + GBN) / NS2) & 1;
#pragma unroll 1
      for (int seg = 0; seg < 2; seg++)
        gemm(std::false_type{}, accF, 1, seg ? 75 - NS2 : 51 + GBN, seg ? NS2 - 1 : 24 - NS2 - GBN, seg ? 0 : rel3, seg ? 0 : rel3, bE3 + 8 * ((34 + GBN) % NS2));
      fold();
      wg_wait<0>();
      pin(accF);
      check_rows<true>(bad, par, accF, [&]() {
#pragma unroll
        for (int g = 0; g < 10; g++) {
          const uint32_t* ph = reinterpret_cast<const uint32_t*>(g_h + (size_t)(bi * 2 + wg) * 81920 + xoff + (g < 8 ? bj * 8192 + (g >> 1) * 2048 : (32 + bj) * 2048) + (g & 1) * 128);
          const uint32_t h0 = ld_rlx(ph), h1 = ld_rlx(ph + 64), bb = ldg_nc1(P.pb2 + (g < 8 ? bj * 64 + g * 8 : 512 + bj * 16 + (g - 8) * 8) + qc * 2);
          accF[4 * g] = blo(h0) + blo(bb); accF[4 * g + 1] = bhi(h0) + bhi(bb);
          accF[4 * g + 2] = blo(h1) + blo(bb); accF[4 * g + 3] = bhi(h1) + bhi(bb);
        }
      }, g_g + (size_t)(bi * 2 + wg) * 196608 + w4 * 512, P.pw2, 640, bj * 64, 512 + bj * 16, lane);
      TSW(14);
      const uint32_t row = w4 * 16 + (lane & 15), stage = ra + 3 * 32768;
#pragma unroll
      for (int u = 0; u < 5; u++) {
        uint32_t o[4];
#pragma unroll
        for (int h = 0; h < 4; h++) o[h] = pack(accF[8 * u + 2 * h], accF[8 * u + 2 * h + 1]);
        const uint32_t ch = (u < 4 ? 2 * u : 0) + (lane >> 4);
        stsm4(stage + (u < 4 ? 0 : 32768) + row * 128 + ((ch ^ (row & 7)) << 4), o[0], o[1], o[2], o[3]);
      }
      fence_async_smem();
      __syncwarp();
      if (elect_one()) {
        tma_st(&P.outM, stage + w4 * 2048, bj * 64, bi * 128 + wg * 64 + w4 * 16);
        tma_st(&P.outR, stage + 32768 + w4 * 2048, 512 + bj * 16, bi * 128 + wg * 64 + w4 * 16);
        bulk_commit();
        bulk_wait_read();
        if (b == 0 && warp == 0) st_flag(g_s.epoch, epoch);
      }
      __syncwarp();
      TSW(15);
      if (warp == 4) TSG(47);
    }
  }
}

typedef CUresult (*EncodeFn)(CUtensorMap*, CUtensorMapDataType, cuuint32_t, void*, const cuuint64_t*, const cuuint64_t*,
                             const cuuint32_t*, const cuuint32_t*, CUtensorMapInterleave, CUtensorMapSwizzle,
                             CUtensorMapL2promotion, CUtensorMapFloatOOBfill);

void make_map(EncodeFn enc, CUtensorMap* m, const void* p, uint64_t cols, uint64_t rows, uint32_t bc, uint32_t br,
              CUtensorMapSwizzle sw = CU_TENSOR_MAP_SWIZZLE_128B) {
  cuuint64_t gd[2] = {cols, rows}, gs[1] = {cols * 2};
  cuuint32_t bd[2] = {bc, br}, es[2] = {1, 1};
  enc(m, CU_TENSOR_MAP_DATA_TYPE_BFLOAT16, 2, const_cast<void*>(p), gd, gs, bd, es, CU_TENSOR_MAP_INTERLEAVE_NONE,
      sw, CU_TENSOR_MAP_L2_PROMOTION_L2_128B, CU_TENSOR_MAP_FLOAT_OOB_FILL_NONE);
}

}

extern "C" void kernel_launch(void* const* d_in, const int* in_sizes, int n_in, void* d_out, int out_size) {
  (void)in_sizes; (void)n_in; (void)out_size;
  void* fn = nullptr;
  cudaDriverEntryPointQueryResult qr;
  cudaGetDriverEntryPoint("cuTensorMapEncodeTiled", &fn, cudaEnableDefault, &qr);
  EncodeFn enc = (EncodeFn)fn;
  Params P;
  P.px = (const __nv_bfloat16*)d_in[0];
  P.pwqkv = (const __nv_bfloat16*)d_in[1];
  P.pwo = (const __nv_bfloat16*)d_in[2];
  P.pw1 = (const __nv_bfloat16*)d_in[4];
  P.pb1 = (const __nv_bfloat16*)d_in[5];
  P.pw2 = (const __nv_bfloat16*)d_in[6];
  P.pb2 = (const __nv_bfloat16*)d_in[7];
  constexpr uint32_t BR = 32;
  make_map(enc, &P.x, P.px, 640, 2048, 64, 128);
  make_map(enc, &P.qkvS, P.pwqkv, 1920, 640, 64, 128);
  make_map(enc, &P.w1S, P.pw1, 1536, 640, 64, 128);
  make_map(enc, &P.qkvM, P.pwqkv, 1920, 640, 64, BR);
  make_map(enc, &P.qkvR, P.pwqkv, 1920, 640, 16, BR);
  make_map(enc, &P.woM, P.pwo, 640, 640, 64, BR);
  make_map(enc, &P.woR, P.pwo, 640, 640, 16, BR);
  make_map(enc, &P.w1M, P.pw1, 1536, 640, 64, BR);
  make_map(enc, &P.w1R, P.pw1, 1536, 640, 32, BR);
  make_map(enc, &P.w2M, P.pw2, 640, 1536, 64, BR);
  make_map(enc, &P.w2R, P.pw2, 640, 1536, 16, BR);
  make_map(enc, &P.outM, d_out, 640, 2048, 64, 16);
  make_map(enc, &P.outR, d_out, 640, 2048, 16, 16);
  cudaFuncSetAttribute(fused_block_kernel<0>, cudaFuncAttributeMaxDynamicSharedMemorySize, SMEM_BYTES);
  cudaFuncSetAttribute(fused_block_kernel<128>, cudaFuncAttributeMaxDynamicSharedMemorySize, SMEM_BYTES);
  cudaLaunchConfig_t cfg = {};
  cfg.gridDim = dim3(132);
  cfg.blockDim = dim3(512);
  cfg.dynamicSmemBytes = SMEM_BYTES;
  cfg.stream = cudaStreamPerThread;
  cudaLaunchAttribute at[1];
  at[0].id = cudaLaunchAttributeClusterDimension;
  at[0].val.clusterDim.x = 2; at[0].val.clusterDim.y = 1; at[0].val.clusterDim.z = 1;
  cfg.attrs = at;
  cfg.numAttrs = 1;
  int ncl = 0;
  cudaOccupancyMaxActiveClusters(&ncl, fused_block_kernel<0>, &cfg);
  if (ncl >= 66) cudaLaunchKernelEx(&cfg, fused_block_kernel<0>, P);
  else cudaLaunchKernelEx(&cfg, fused_block_kernel<128>, P);
}
```
